```python
import torch

def _softmax(x, axis=-1):
    return torch.softmax(x, dim=axis)
def _gelu(x):
    return torch.nn.functional.gelu(x, approximate="tanh")
def _silu(x):
    return torch.nn.functional.silu(x)
def _sigmoid(x):
    return torch.sigmoid(x)
def _layernorm(x, axis=-1, eps=1e-5):
    m = x.mean(dim=axis, keepdim=True)
    v = x.var(dim=axis, keepdim=True, unbiased=False)
    return (x - m) / torch.sqrt(v + eps)
def _scatter_add(tgt, idx, src, axis=0):
    return tgt.clone().index_add_(axis, idx, src)
def _segment_sum(src, seg, n):
    out = torch.zeros((n,) + src.shape[1:], dtype=src.dtype)
    return out.index_add_(0, seg, src)
def _pad(x, pw):
    flat = tuple(v for pair in reversed(pw) for v in pair)
    return torch.nn.functional.pad(x, flat)

kernel_name = 'concat_heads__mha_block_cached__gqa_block_cached__near_ridge'

def setup_inputs():

    _w = (lambda a: (lambda t: t.to(torch.bfloat16) if t.is_floating_point() else t)(torch.as_tensor(a)))
    def _A_setup():
        B, Sq, D = 8, 144, 512
        H, Sk, Dh = 32, 1024, 128
        return {
            "x": _w((lambda *s: torch.randn(*s, dtype=torch.bfloat16) * 0.8)(B, Sq, D)),
            "k_cache": _w((lambda *s: torch.randn(*s, dtype=torch.bfloat16) * 0.8)(B, H, Sk, Dh)),
            "v_cache": _w((lambda *s: torch.randn(*s, dtype=torch.bfloat16) * 0.05)(B, H, Sk, Dh)),
            "wq": _w((lambda *s: torch.randn(*s, dtype=torch.bfloat16) * 0.8)(D, H * Dh) * (D ** -0.5)),
            "wo": _w((lambda *s: torch.randn(*s, dtype=torch.bfloat16) * 0.05)(H * Dh, D) * ((H * Dh) ** -0.5)),
        }
    _A_in = _A_setup()

    def _B_setup():
        B, Sq, D = 8, 144, 512
        Hq, Hkv, Sk, Dh = 32, 32, 1024, 128
        assert Hq % Hkv == 0, (Hq, Hkv)
        return {
            "x": _w((lambda *s: torch.randn(*s, dtype=torch.bfloat16) * 0.8)(B, Sq, D)),
            "k_cache": _w((lambda *s: torch.randn(*s, dtype=torch.bfloat16) * 0.8)(B, Hkv, Sk, Dh)),
            "v_cache": _w((lambda *s: torch.randn(*s, dtype=torch.bfloat16) * 0.05)(B, Hkv, Sk, Dh)),
            "wq": _w((lambda *s: torch.randn(*s, dtype=torch.bfloat16) * 0.8)(D, Hq * Dh) * (D ** -0.5)),
            "wo": _w((lambda *s: torch.randn(*s, dtype=torch.bfloat16) * 0.05)(Hq * Dh, D) * ((Hq * Dh) ** -0.5)),
        }
    _B_in = _B_setup()

    return {
        "A_x": _A_in["x"],
        "A_k_cache": _A_in["k_cache"],
        "A_v_cache": _A_in["v_cache"],
        "A_wq": _A_in["wq"],
        "A_wo": _A_in["wo"],
        "B_x": _B_in["x"],
        "B_k_cache": _B_in["k_cache"],
        "B_v_cache": _B_in["v_cache"],
        "B_wq": _B_in["wq"],
        "B_wo": _B_in["wo"],
    }

def reference(A_x, A_k_cache, A_v_cache, A_wq, A_wo, B_x, B_k_cache, B_v_cache, B_wq, B_wo):
    def _A_ref(x, k_cache, v_cache, wq, wo):
        B, Sq, D = x.shape
        H, Dh = 32, 128
        q = (lambda x, *d: x.permute(*d))((x @ wq).reshape(B, Sq, H, Dh), 0, 2, 1, 3)
        scores = torch.einsum("bhqd,bhkd->bhqk", q, k_cache) * (Dh ** -0.5)
        p = _softmax(scores, axis=-1)
        o = torch.einsum("bhqk,bhkd->bhqd", p, v_cache)
        return (lambda x, *d: x.permute(*d))(o, 0, 2, 1, 3).reshape(B, Sq, H * Dh) @ wo

    def _B_ref(x, k_cache, v_cache, wq, wo):
        B, Sq, D = x.shape
        Hq, Dh = 32, 128
        Hkv = k_cache.shape[1]
        rep = Hq // Hkv
        q = (lambda x, *d: x.permute(*d))((x @ wq).reshape(B, Sq, Hq, Dh), 0, 2, 1, 3)
        k = (lambda x, n, axis: torch.repeat_interleave(x, n, dim=axis))(k_cache, rep, axis=1)
        v = (lambda x, n, axis: torch.repeat_interleave(x, n, dim=axis))(v_cache, rep, axis=1)
        scores = torch.einsum("bhqd,bhkd->bhqk", q, k) * (Dh ** -0.5)
        p = _softmax(scores, axis=-1)
        o = torch.einsum("bhqk,bhkd->bhqd", p, v)
        return (lambda x, *d: x.permute(*d))(o, 0, 2, 1, 3).reshape(B, Sq, Hq * Dh) @ wo

    a = _A_ref(A_x, A_k_cache, A_v_cache, A_wq, A_wo)
    b = _B_ref(B_x, B_k_cache, B_v_cache, B_wq, B_wo)
    return torch.concatenate([a, b], axis=-1)
```

```cpp
#include <cuda_runtime.h>
#include <cuda_bf16.h>
#include <cuda.h>
#include <stdint.h>

namespace {

constexpr int SQ = 144, DM = 512, NH = 32, SK = 1024, DH = 128;
constexpr int NCTA = 128;
constexpr int KV_STAGES = 6;
constexpr int KV_FIRST = 4;
constexpr int PJ_STAGES = 4;
constexpr int PJ_FINAL = 7;
constexpr int KV_BYTES = 16384;
constexpr int PJ_A_BYTES = 8192;
constexpr int PJ_B_BYTES = 18432;
constexpr int PJ_BYTES = PJ_A_BYTES + PJ_B_BYTES;
constexpr int NSTEPS = 128;

constexpr int OFF_PJ = 0;
constexpr int OFF_KV = OFF_PJ + PJ_STAGES * PJ_BYTES;
constexpr int OFF_SUM = OFF_PJ + 2 * PJ_BYTES + PJ_A_BYTES;
constexpr int OFF_OUT = OFF_PJ + 4 * PJ_BYTES;
constexpr uint32_t FIN_ORDER = 0x3265410u;
constexpr int OFF_TQ = OFF_KV + KV_STAGES * KV_BYTES;
constexpr int OFF_PT = OFF_TQ + 4 * 4096;
constexpr int OFF_RED = OFF_PT + 2 * 2048;
constexpr int OFF_CTL = OFF_RED + 1024;
constexpr int OFF_LOC = OFF_CTL + 64;
constexpr int OFF_BAR = OFF_LOC + 128;
constexpr int Q0_BYTES = 2 * PJ_A_BYTES + PJ_B_BYTES;
constexpr int PJ_BARS = PJ_FINAL + 4;
constexpr int NBARS = 2 * KV_STAGES + 2 * PJ_BARS + 4 + 4 + 32 + 2;
static_assert(3 * Q0_BYTES <= OFF_KV && 4 * Q0_BYTES <= OFF_KV + 2 * KV_BYTES, "first stages");
static_assert(PJ_FINAL * PJ_BYTES <= OFF_KV + 5 * KV_BYTES && (128 + KV_FIRST) % KV_STAGES == 0, "ring arithmetic");
constexpr int SMEM_BYTES = OFF_BAR + NBARS * 8 + 1024;
static_assert(OFF_CTL % 1024 == 0 && OFF_BAR - OFF_CTL + NBARS * 8 <= 1024, "control block");
static_assert(SMEM_BYTES <= 232448, "smem");

constexpr int KV_FLY = 3, FLY0 = 4;
constexpr int BAL_L1 = 3, BAL_L2 = 5;
constexpr int STAGGER = 2;
constexpr int PROG_END = 125;
constexpr int PF_T0 = 1000, PF_GAP = 800, PF_N = 6;
constexpr int WPF_T0 = 7000, WPF_GAP = 1000;
constexpr int PASS_W = 2, PASS_X1 = 6, PASS_X2 = 3;
constexpr int VREL_AT = 4;
constexpr int T_W0 = 4, T_X0 = 5, T_W1 = 6, T_X1 = 7;
constexpr int B_FIN = 8;
constexpr int NAUX = NSTEPS - 16;
template <bool B> struct BoolC { static constexpr bool value = B; };
constexpr unsigned SPIN_LIMIT = 1u << 20;

struct Ctl {
  unsigned done, pad0[31];
  unsigned prog, pad1[31];
  unsigned ticket;
};
struct Ptrs { __nv_bfloat16* out; uint8_t* x; Ctl* ctl; const uint8_t* kv[4]; const uint8_t* wq[2]; };
struct Params {
  CUtensorMap k[2], v[2], x[2], wq[2], wo[2], o, ot;
};

constexpr int XPAGES = (NCTA + 6) / 7;
__device__ uint8_t g_x[(XPAGES + 1) << 21];
__device__ __forceinline__ int x_block(int b, int u) { return ((b / 7) * 4 + b * 4 + u) * 16; }
__device__ __forceinline__ int x_tail(int blk) { return (blk | 511) - 63 + ((blk >> 3) & 62); }
__device__ __forceinline__ int x_near(int c, int hn) { return c | ((__popc(c & 0xB3) ^ hn) & 1); }
constexpr uint32_t X_COMMON = (XPAGES * 32 - 16) * 65536;
__device__ __forceinline__ unsigned* x_flags(uint8_t* x, int g) {
  return reinterpret_cast<unsigned*>(x + X_COMMON + 3 * 4096 - (g >> 3) * (4096 + 1024) + g * 128);
}
__device__ __align__(128) Ctl g_ctl;

__device__ __forceinline__ uint32_t smem_u32(const void* p) { return (uint32_t)__cvta_generic_to_shared(p); }
__device__ __forceinline__ void mbar_init(uint32_t bar, uint32_t cnt) {
  asm volatile("mbarrier.init.shared::cta.b64 [%0], %1;" ::"r"(bar), "r"(cnt) : "memory");
}
__device__ __forceinline__ void mbar_expect_tx(uint32_t bar, uint32_t bytes) {
  asm volatile("mbarrier.arrive.expect_tx.shared::cta.b64 _, [%0], %1;" ::"r"(bar), "r"(bytes) : "memory");
}
__device__ __forceinline__ void mbar_arrive(uint32_t bar) {
  asm volatile("mbarrier.arrive.shared::cta.b64 _, [%0];" ::"r"(bar) : "memory");
}
__device__ __forceinline__ void mbar_arrive_n(uint32_t bar, uint32_t n) {
  asm volatile("mbarrier.arrive.shared::cta.b64 _, [%0], %1;" ::"r"(bar), "r"(n) : "memory");
}
__device__ __forceinline__ void mbar_arrive_cluster(uint32_t bar, uint32_t cta, uint32_t n) {
  asm volatile("{\n.reg .b32 ra;\nmapa.shared::cluster.u32 ra, %0, %1;\nmbarrier.arrive.shared::cluster.b64 _, [ra], %2;\n}"
               ::"r"(bar), "r"(cta), "r"(n) : "memory");
}
__device__ __forceinline__ uint32_t lds_volatile(uint32_t a) {
  uint32_t v;
  asm volatile("ld.volatile.shared.u32 %0, [%1];" : "=r"(v) : "r"(a) : "memory");
  return v;
}
__device__ __forceinline__ void sts_volatile(uint32_t a, uint32_t v) {
  asm volatile("st.volatile.shared.u32 [%0], %1;" ::"r"(a), "r"(v) : "memory");
}
__device__ __forceinline__ bool spin_giveup(uint32_t& it, uint32_t ctl) {
  if (++it > SPIN_LIMIT) sts_volatile(ctl & ~1023u, 1u);
  return lds_volatile(ctl & ~1023u) != 0;
}
__device__ __forceinline__ void mbar_wait(uint32_t bar, uint32_t parity) {
  uint32_t ok, it = 0;
  while (true) {
    asm volatile("{\n.reg .pred p;\nmbarrier.try_wait.parity.shared::cta.b64 p, [%1], %2;\nselp.u32 %0,1,0,p;\n}"
                 : "=r"(ok) : "r"(bar), "r"(parity) : "memory");
    if (ok) break;
    if (spin_giveup(it, bar)) break;
  }
}
__device__ __forceinline__ void mbar_wait2(uint32_t bar0, uint32_t par0, uint32_t bar1, uint32_t par1) {
  uint32_t ok, it = 0;
  while (true) {
    asm volatile("{\n.reg .pred p, q;\nmbarrier.try_wait.parity.shared::cta.b64 p, [%1], %2;\n"
                 "mbarrier.try_wait.parity.shared::cta.b64 q, [%3], %4;\nand.pred p, p, q;\nselp.u32 %0,1,0,p;\n}"
                 : "=r"(ok) : "r"(bar0), "r"(par0), "r"(bar1), "r"(par1) : "memory");
    if (ok) break;
    if (spin_giveup(it, bar0)) break;
  }
}
__device__ __forceinline__ uint32_t mbar_try(uint32_t bar, uint32_t parity, uint32_t ns) {
  uint32_t ok;
  if (ns)
    asm volatile("{\n.reg .pred p;\nmbarrier.try_wait.parity.shared::cta.b64 p, [%1], %2, %3;\nselp.u32 %0,1,0,p;\n}"
                 : "=r"(ok) : "r"(bar), "r"(parity), "r"(ns) : "memory");
  else
    asm volatile("{\n.reg .pred p;\nmbarrier.try_wait.parity.shared::cta.b64 p, [%1], %2;\nselp.u32 %0,1,0,p;\n}"
                 : "=r"(ok) : "r"(bar), "r"(parity) : "memory");
  return ok;
}
__device__ __forceinline__ uint32_t mbar_test(uint32_t bar, uint32_t parity) {
  uint32_t ok;
  asm volatile("{\n.reg .pred p;\nmbarrier.test_wait.parity.shared::cta.b64 p, [%1], %2;\nselp.u32 %0,1,0,p;\n}"
               : "=r"(ok) : "r"(bar), "r"(parity) : "memory");
  return ok;
}
__device__ __forceinline__ void bar_sync(int id, int n) { asm volatile("bar.sync %0, %1;" ::"r"(id), "r"(n) : "memory"); }
__device__ __forceinline__ bool elect_one() {
  uint32_t r;
  asm volatile("{\n.reg .pred p;\nelect.sync _|p, 0xffffffff;\nselp.u32 %0, 1, 0, p;\n}" : "=r"(r));
  return r != 0;
}
__device__ __forceinline__ void bar_arrive(int id, int n) { asm volatile("bar.arrive %0, %1;" ::"r"(id), "r"(n) : "memory"); }
__device__ __forceinline__ void fence_async_smem() { asm volatile("fence.proxy.async.shared::cta;" ::: "memory"); }
__device__ __forceinline__ void fence_async_global() { asm volatile("fence.proxy.async.global;" ::: "memory"); }

__device__ __forceinline__ void tma_2d(uint32_t dst, const CUtensorMap* m, int c0, int c1, uint32_t bar) {
  asm volatile("cp.async.bulk.tensor.2d.shared::cluster.global.mbarrier::complete_tx::bytes [%0], [%1, {%3, %4}], [%2];"
               ::"r"(dst), "l"(m), "r"(bar), "r"(c0), "r"(c1) : "memory");
}
__device__ __forceinline__ void tma_2d_mc(uint32_t dst, const CUtensorMap* m, int c0, int c1, uint32_t bar, uint16_t mask) {
  asm volatile("cp.async.bulk.tensor.2d.shared::cluster.global.mbarrier::complete_tx::bytes.multicast::cluster [%0], [%1, {%3, %4}], [%2], %5;"
               ::"r"(dst), "l"(m), "r"(bar), "r"(c0), "r"(c1), "h"(mask) : "memory");
}
__device__ __forceinline__ void tma_o_mc(uint32_t dst, const CUtensorMap* m, int c0, uint32_t loc, uint32_t rank, uint32_t bar) {
  asm volatile("cp.async.bulk.tensor.4d.shared::cluster.global.mbarrier::complete_tx::bytes.multicast::cluster [%0], [%1, {%3, %4, %4, %5}], [%2], %6;"
               ::"r"(dst + rank * 8192), "l"(m), "r"(bar), "r"(c0), "r"(0), "r"(loc & 0xffffu), "h"((uint16_t)3) : "memory");
  asm volatile("cp.async.bulk.tensor.3d.shared::cluster.global.mbarrier::complete_tx::bytes.multicast::cluster [%0], [%1, {%3, %4, %5}], [%2], %6;"
               ::"r"(dst + 16384 + rank * 1024), "l"(m + 1), "r"(bar), "r"(c0), "r"(rank * 8), "r"(loc >> 16), "h"((uint16_t)3) : "memory");
}
__device__ __forceinline__ void tma_3d_hint(uint32_t dst, const CUtensorMap* m, int c0, int c1, int c2, uint32_t bar, uint64_t pol) {
  asm volatile("cp.async.bulk.tensor.3d.shared::cluster.global.mbarrier::complete_tx::bytes.L2::cache_hint [%0], [%1, {%3, %4, %5}], [%2], %6;"
               ::"r"(dst), "l"(m), "r"(bar), "r"(c0), "r"(c1), "r"(c2), "l"(pol) : "memory");
}
__device__ __forceinline__ void tma_5d(uint32_t dst, const CUtensorMap* m, int c0, int c4, uint32_t bar) {
  asm volatile("cp.async.bulk.tensor.5d.shared::cluster.global.mbarrier::complete_tx::bytes [%0], [%1, {%3, %4, %4, %4, %5}], [%2];"
               ::"r"(dst), "l"(m), "r"(bar), "r"(c0), "r"(0), "r"(c4) : "memory");
}

__device__ __forceinline__ void pf_2d(const CUtensorMap* m, int c0, int c1) {
  asm volatile("cp.async.bulk.prefetch.tensor.2d.L2.global.tile [%0, {%1, %2}];" ::"l"(m), "r"(c0), "r"(c1) : "memory");
}

__device__ __forceinline__ uint64_t make_desc(uint32_t a16, uint32_t lbo, uint32_t sbo) {
  uint64_t d;
  asm("mov.b64 %0, {%1, %2};" : "=l"(d) : "r"(a16 + ((lbo >> 4) << 16)), "r"((sbo >> 4) | (1u << 30)));
  return d;
}
__device__ __forceinline__ void wg_fence() { asm volatile("wgmma.fence.sync.aligned;" ::: "memory"); }
__device__ __forceinline__ void wg_commit() { asm volatile("wgmma.commit_group.sync.aligned;" ::: "memory"); }
template <int N> __device__ __forceinline__ void wg_wait() { asm volatile("wgmma.wait_group.sync.aligned %0;" ::"n"(N) : "memory"); }

__device__ __forceinline__ uint32_t pack_bf16(float lo, float hi) {
  uint32_t r;
  asm("cvt.rn.bf16x2.f32 %0, %1, %2;" : "=r"(r) : "f"(hi), "f"(lo));
  return r;
}
__device__ __forceinline__ float ex2(float x) {
  float y;
  asm volatile("ex2.approx.ftz.f32 %0, %1;" : "=f"(y) : "f"(x));
  return y;
}
__device__ __forceinline__ uint32_t movmat(uint32_t a) {
  uint32_t d;
  asm volatile("movmatrix.sync.aligned.m8n8.trans.b16 %0, %1;" : "=r"(d) : "r"(a));
  return d;
}
__device__ __forceinline__ void stsm_x4_t(uint32_t addr, uint32_t a, uint32_t b, uint32_t c, uint32_t d) {
  asm volatile("stmatrix.sync.aligned.m8n8.x4.trans.shared.b16 [%0], {%1,%2,%3,%4};" ::"r"(addr), "r"(a), "r"(b), "r"(c), "r"(d) : "memory");
}

template <bool MX> __device__ __forceinline__ float colred(float v0, float v1, float v2, float v3, int ln) {
  const bool hi = ln & 16, mid = ln & 8;
  float a = hi ? v2 : v0, b = hi ? v3 : v1;
  const float x = __shfl_xor_sync(0xffffffffu, hi ? v0 : v2, 16), y = __shfl_xor_sync(0xffffffffu, hi ? v1 : v3, 16);
  a = MX ? fmaxf(a, x) : a + x;
  b = MX ? fmaxf(b, y) : b + y;
  float k = mid ? b : a;
  const float z = __shfl_xor_sync(0xffffffffu, mid ? a : b, 8);
  k = MX ? fmaxf(k, z) : k + z;
  const float q = __shfl_xor_sync(0xffffffffu, k, 4);
  return MX ? fmaxf(k, q) : k + q;
}

#define F4(a, i) "+f"(a[i]), "+f"(a[(i) + 1]), "+f"(a[(i) + 2]), "+f"(a[(i) + 3])
#define F8(a, i) F4(a, i), F4(a, (i) + 4)
#define F16(a, i) F8(a, i), F8(a, (i) + 8)
#define F32(a, i) F16(a, i), F16(a, (i) + 16)

__device__ __forceinline__ void wgmma_qk(float (&d)[32], const uint32_t (&a)[4], uint64_t db, int scale_d) {
  asm volatile(
      "{\n.reg .pred p;\nsetp.ne.b32 p, %37, 0;\n"
      "wgmma.mma_async.sync.aligned.m64n64k16.f32.bf16.bf16 "
      "{%0,%1,%2,%3,%4,%5,%6,%7,%8,%9,%10,%11,%12,%13,%14,%15,%16,%17,%18,%19,%20,%21,%22,%23,%24,%25,%26,%27,%28,%29,%30,%31},"
      "{%32,%33,%34,%35}, %36, p, 1, 1, 0;\n}"
      : F32(d, 0)
      : "r"(a[0]), "r"(a[1]), "r"(a[2]), "r"(a[3]), "l"(db), "r"(scale_d));
}
__device__ __forceinline__ void wgmma_pv(float (&d)[64], const uint32_t (&a)[4], uint64_t db, int scale_d) {
  asm volatile(
      "{\n.reg .pred p;\nsetp.ne.b32 p, %69, 0;\n"
      "wgmma.mma_async.sync.aligned.m64n128k16.f32.bf16.bf16 "
      "{%0,%1,%2,%3,%4,%5,%6,%7,%8,%9,%10,%11,%12,%13,%14,%15,%16,%17,%18,%19,%20,%21,%22,%23,%24,%25,%26,%27,%28,%29,%30,%31,"
      "%32,%33,%34,%35,%36,%37,%38,%39,%40,%41,%42,%43,%44,%45,%46,%47,%48,%49,%50,%51,%52,%53,%54,%55,%56,%57,%58,%59,%60,%61,%62,%63},"
      "{%64,%65,%66,%67}, %68, p, 1, 1, 1;\n}"
      : F32(d, 0), F32(d, 32)
      : "r"(a[0]), "r"(a[1]), "r"(a[2]), "r"(a[3]), "l"(db), "r"(scale_d));
}
__device__ __forceinline__ void wgmma_q0(float (&d)[64], uint64_t da, uint64_t db, int scale_d) {
  asm volatile(
      "{\n.reg .pred p;\nsetp.ne.b32 p, %66, 0;\n"
      "wgmma.mma_async.sync.aligned.m64n128k16.f32.bf16.bf16 "
      "{%0,%1,%2,%3,%4,%5,%6,%7,%8,%9,%10,%11,%12,%13,%14,%15,%16,%17,%18,%19,%20,%21,%22,%23,%24,%25,%26,%27,%28,%29,%30,%31,"
      "%32,%33,%34,%35,%36,%37,%38,%39,%40,%41,%42,%43,%44,%45,%46,%47,%48,%49,%50,%51,%52,%53,%54,%55,%56,%57,%58,%59,%60,%61,%62,%63},"
      "%64, %65, p, 1, 1, 0, 1;\n}"
      : F32(d, 0), F32(d, 32)
      : "l"(da), "l"(db), "r"(scale_d));
}
template <int TA>
__device__ __forceinline__ void wgmma_n16(float (&d)[8], uint64_t da, uint64_t db, int scale_d) {
  asm volatile(
      "{\n.reg .pred p;\nsetp.ne.b32 p, %10, 0;\n"
      "wgmma.mma_async.sync.aligned.m64n16k16.f32.bf16.bf16 "
      "{%0,%1,%2,%3,%4,%5,%6,%7}, %8, %9, p, 1, 1, %11, 0;\n}"
      : F8(d, 0)
      : "l"(da), "l"(db), "r"(scale_d), "n"(TA));
}
__device__ __forceinline__ void wgmma_n144(float (&d)[72], uint64_t da, uint64_t db, int scale_d) {
  asm volatile(
      "{\n.reg .pred p;\nsetp.ne.b32 p, %74, 0;\n"
      "wgmma.mma_async.sync.aligned.m64n144k16.f32.bf16.bf16 "
      "{%0,%1,%2,%3,%4,%5,%6,%7,%8,%9,%10,%11,%12,%13,%14,%15,%16,%17,%18,%19,%20,%21,%22,%23,%24,%25,%26,%27,%28,%29,%30,%31,"
      "%32,%33,%34,%35,%36,%37,%38,%39,%40,%41,%42,%43,%44,%45,%46,%47,%48,%49,%50,%51,%52,%53,%54,%55,%56,%57,%58,%59,%60,%61,%62,%63,"
      "%64,%65,%66,%67,%68,%69,%70,%71},"
      "%72, %73, p, 1, 1, 1, 0;\n}"
      : F32(d, 0), F32(d, 32), F8(d, 64)
      : "l"(da), "l"(db), "r"(scale_d));
}

constexpr float SM_SCALE_LOG2 = 0.08838834764831845f * 1.4426950408889634f;
constexpr float RESCALE_LOG2 = 8.f;
constexpr float RESCALE_SUM = 512.f;

__global__ void __launch_bounds__(512, 1)
fused_attn_kernel(const __grid_constant__ Ptrs ptr, const __grid_constant__ Params prm) {
  extern __shared__ uint8_t smem_raw[];
  const uint32_t sbase = (smem_u32(smem_raw) + 1023u) & ~1023u;
  uint8_t* sgen = smem_raw + (sbase - smem_u32(smem_raw));
  const uint32_t dbase = (sbase & 0x3FFFFu) >> 4;

  const int tid = threadIdx.x;
  const int wg = __shfl_sync(0xffffffffu, tid >> 7, 0);
  const int warp = __shfl_sync(0xffffffffu, (tid >> 5) & 3, 0);
  const int lane = tid & 31;
  const uint32_t crank = blockIdx.x & 1;

  const uint32_t bar_kv_full = sbase + OFF_BAR;
  const uint32_t bar_kv_empty = bar_kv_full + 8 * KV_STAGES;
  const uint32_t bar_pj_full = bar_kv_empty + 8 * KV_STAGES;
  const uint32_t bar_pj_empty = bar_pj_full + 8 * PJ_BARS;
  const uint32_t bar_q_full = bar_pj_empty + 8 * PJ_BARS;
  const uint32_t bar_o_done = bar_q_full + 8 * 4;
  const uint32_t bar_head = bar_o_done + 8 * 4;
  const uint32_t bar_item = bar_head + 8 * 32;
  const uint32_t bar_sum = bar_item + 8;
  const uint32_t a_progress = sbase + OFF_CTL + 8;
  const uint32_t a_item = sbase + OFF_CTL + 12;
  const uint32_t a_near = sbase + OFF_CTL + 16;
  const uint32_t a_lat = sbase + OFF_CTL + 32;
  const uint32_t a_loc = sbase + OFF_LOC;

  if (tid == 32) {
    const int br = blockIdx.x >> 6, b = (blockIdx.x >> 3) & 7, j = blockIdx.x & 7;
    pf_2d(&prm.x[br], j * 64, b * SQ);
    pf_2d(&prm.x[br], j * 64, b * SQ + 72);
    for (int ps = b; ps < 16; ps += 8) pf_2d(&prm.wq[br], ((ps >> 4) * 8 + j) * DH + ((ps >> 3) & 1) * 64, (ps & 7) * 64);
  }
  if (tid == 160 && crank == 0) asm volatile("red.relaxed.gpu.global.add.u32 [%0], 0;" ::"l"(&ptr.ctl->ticket) : "memory");
  if (tid == 0) {
    for (int i = 0; i < KV_STAGES; i++) { mbar_init(bar_kv_full + 8 * i, 1); mbar_init(bar_kv_empty + 8 * i, 12); }
    for (int i = 0; i < KV_FIRST; i++) mbar_arrive(bar_kv_full + 8 * i);
    for (int i = 2; i < KV_FIRST; i++) mbar_arrive_n(bar_kv_empty + 8 * i, 12);
  } else if (tid == 64) {
    for (int i = 0; i < PJ_BARS; i++) { mbar_init(bar_pj_full + 8 * i, 1); mbar_init(bar_pj_empty + 8 * i, i < PJ_FINAL ? 8 : 24); }
    for (int i = 0; i < PJ_FINAL; i++) mbar_arrive(bar_pj_full + 8 * i);
    for (int i = 0; i < PJ_STAGES; i++) mbar_arrive_n(bar_pj_empty + 8 * i, 8);
    mbar_init(bar_sum, 8);
    mbar_init(bar_item, 2);
    mbar_expect_tx(bar_item, 4);
    asm volatile("fence.mbarrier_init.release.cluster;" ::: "memory");
  } else if (tid == 96) {
    sts_volatile(sbase + OFF_CTL, 0u);
    sts_volatile(a_progress, 0u);
    sts_volatile(sbase + OFF_CTL + 20, 999u);
    for (int i = 0; i < 4; i++) { mbar_init(bar_q_full + 8 * i, 128); mbar_init(bar_o_done + 8 * i, 12); }
    for (int i = 0; i < 12; i++) mbar_init(bar_head + 8 * i, 1);
  } else if (tid == 256) {
    for (int i = 12; i < 32; i++) mbar_init(bar_head + 8 * i, 1);
  }
  __syncthreads();
  asm volatile("barrier.cluster.arrive.relaxed.aligned;" ::: "memory");
  auto cluster_wait = []() { asm volatile("barrier.cluster.wait.aligned;" ::: "memory"); };
  auto share = [&]() {
    mbar_wait(bar_item, 0);
    return (int)(__shfl_sync(0xffffffffu, lds_volatile(a_item), 0) * 2 + crank);
  };
  int cta = blockIdx.x;
  auto first_q = [&](auto mma) {
    uint32_t rb;
    asm volatile("mapa.shared::cluster.u32 %0, %1, %2;" : "=r"(rb) : "r"(bar_pj_empty + 8 * PJ_FINAL), "r"(lane & 1));
#pragma unroll 1
    for (int k = 0; k < 8; k++) {
      mbar_wait(bar_pj_full + 8 * (PJ_FINAL + ((k + 3) & 3)), k >> 2);
      wg_fence();
      mma(dbase + ((((k + 3) & 3) * Q0_BYTES) >> 4), k);
      wg_commit();
      wg_wait<0>();
      if (lane < 2) {
        if (k == 4) mbar_arrive(bar_kv_empty + 8 * lane);
        else asm volatile("mbarrier.arrive.shared::cluster.b64 _, [%0];" ::"r"(rb + 8 * ((k + 3) & 3)) : "memory");
      }
    }
  };

  const uint32_t st_off = (uint32_t)((((lane >> 4) * 8 + (lane & 7)) * 128) + (((2 * warp + ((lane >> 3) & 1)) ^ (lane & 7)) << 4));

  if (wg == 0) {
    asm volatile("setmaxnreg.dec.sync.aligned.u32 24;");
    if (warp == 0) {
      uint64_t pol;
      asm volatile("createpolicy.fractional.L2::evict_first.b64 %0, 1.0;" : "=l"(pol));
      int slot = KV_FIRST; uint32_t ph = 1;
      int landed = 0, fslot = KV_FIRST; uint32_t fph = 0;
      int fly = FLY0;
      cluster_wait();
      {
        const size_t off = (size_t)(((blockIdx.x >> 3) & 7) * NH + (blockIdx.x & 7)) * (SK * DH * 2) + lane * 128;
        uint32_t t0 = clock() + PF_T0;
        if (lane < 8) asm volatile("prefetch.tensormap [%0];" ::"l"(&prm.k[0] + (lane < 4 ? lane : lane + 4)) : "memory");
        for (int i = 0; i < PF_N; i++) {
          while ((int)(clock() - t0) < 0) __nanosleep(20);
          t0 += PF_GAP;
          const bool isv = i != 0 && (i & 1) == 0;
          const uint8_t* p = ptr.kv[isv * 2 + (blockIdx.x >> 6)] + off + (isv ? (i >> 1) - 1 : (i + 1) >> 1) * KV_BYTES;
#pragma unroll
          for (int j = 0; j < 4; j++) asm volatile("prefetch.global.L2 [%0];" ::"l"(p + j * 4096) : "memory");
        }
        mbar_wait(bar_kv_empty, 0);
      }
      for (int i = 0; i < 128; i++) {
        const bool isv = (i == 127) || (i != 0 && (i & 1) == 0);
        const int g = (i == 127) ? 63 : (isv ? (i >> 1) - 1 : (i + 1) >> 1);
        if (i == KV_STAGES) cta = share();
        const int c = g < 16 ? blockIdx.x : cta;
        const int row = (((c >> 3) & 7) * NH + (g >> 4) * 8 + (c & 7)) * SK + (g & 15) * 64;
        const CUtensorMap* m = &prm.k[0] + (isv * 2 + (c >> 6));
        const uint32_t fb = bar_kv_full + 8 * slot, dst = sbase + OFF_KV + slot * KV_BYTES;
        mbar_wait(bar_kv_empty + 8 * slot, ph);
        if (elect_one()) mbar_expect_tx(fb, KV_BYTES);
        while (i - landed >= fly) {
          mbar_wait(bar_kv_full + 8 * fslot, fph);
          landed++;
          if (++fslot == KV_STAGES) { fslot = 0; fph ^= 1; }
        }
        if (elect_one()) {
          tma_3d_hint(dst, m, 0, row, 0, fb, pol);
          asm volatile("red.relaxed.gpu.global.add.u32 [%0], 1;" ::"l"(&ptr.ctl->prog) : "memory");
        }
        if (++slot == KV_STAGES) { slot = 0; ph ^= 1; }
        const int prog = (int)lds_volatile(a_progress);
        const int lead = i + 1 - prog - ((STAGGER * (3 - (cta & 6))) >> 2);
        if (i >= FLY0 - 1) fly = lead >= BAL_L2 ? KV_FLY - 2 : (lead >= BAL_L1 ? KV_FLY - 1 : (lead <= 0 ? KV_FLY + 1 : KV_FLY));
      }
      for (int i = 0; i < 5; i++) {
        mbar_wait(bar_kv_empty + 8 * i, ph);
        if ((i == 1 || i >= 3) && lane < 2) mbar_arrive_cluster(bar_pj_empty + 8 * (PJ_STAGES + (i >> 1)), lane, 4);
      }
    } else if (warp == 1) {
      {
        int slot = 0; uint32_t ph = 0, loc = 0;
        cluster_wait();
        for (int k = 0; k < 8; k++) {
          const uint32_t dstA = sbase + ((k + 3) & 3) * Q0_BYTES, fb = bar_pj_full + 8 * (PJ_FINAL + ((k + 3) & 3));
          if (k >= 4) mbar_wait(fb + 8 * PJ_BARS, 0);
          if (elect_one()) {
            mbar_expect_tx(fb, Q0_BYTES);
            tma_2d(dstA, &prm.wq[cta >> 6], (cta & 7) * DH, k * 64, fb);
            tma_2d_mc(dstA + 2 * PJ_A_BYTES + crank * (PJ_B_BYTES / 2), &prm.x[cta >> 6], k * 64, ((cta >> 3) & 7) * SQ + crank * 72, fb, (uint16_t)3);
            tma_2d(dstA + PJ_A_BYTES, &prm.wq[cta >> 6], (cta & 7) * DH + 64, k * 64, fb);
          }
        }
        for (int ps = 16; ps < NAUX; ps++) {
          if (ps < 19) mbar_wait(bar_pj_empty + 8 * (PJ_FINAL + ps - 16), 1);
          if (ps == 16) {
            cta = share();
            for (int it = 0; it < 64 && !mbar_try(bar_kv_full + 8 * 3, 1, 100); it++) {}
          }
          const int jj = cta & 7, branch = cta >> 6;
          const uint32_t dstA = sbase + OFF_PJ + slot * PJ_BYTES;
          const uint32_t fb = bar_pj_full + 8 * slot;
          if (ps < 64) {
            const int k0 = ((ps + ((ps >> 1) & 4)) & 7) * 64;
            const bool ldx = (ps & 4) || ps < 20;
            mbar_wait(fb + 8 * PJ_BARS, ph);
            if (elect_one()) {
              mbar_expect_tx(fb, ldx ? PJ_BYTES : PJ_A_BYTES);
              tma_2d(dstA, &prm.wq[branch], ((ps >> 4) * 8 + jj) * DH + ((ps >> 3) & 1) * 64, k0, fb);
              if (ldx) tma_2d_mc(dstA + PJ_A_BYTES + crank * (PJ_B_BYTES / 2), &prm.x[branch], k0, ((cta >> 3) & 7) * SQ + crank * 72, fb, (uint16_t)3);
            }
          } else {
            const int hi = (ps - 64) >> 1, hh = (hi & 24) + ((hi + (hi < 24 ? jj & 6 : 0)) & 7);
            mbar_wait(bar_pj_empty + 8 * slot, ph);
            if (elect_one()) {
              mbar_expect_tx(fb, PJ_BYTES);
              tma_5d(dstA, &prm.wo[branch], jj * 64, hh * 4 + (ps & 1) * 2, fb);
            }
            if (!(ps & 1)) {
              mbar_wait(bar_head + 8 * hh, 0);
              loc = lds_volatile(a_loc + 4 * hh);
            }
            if (elect_one()) tma_o_mc(dstA + PJ_A_BYTES, &prm.o, (ps & 1) * 64, loc, crank, fb);
          }
          if (++slot == PJ_STAGES) { slot = 0; ph ^= 1; }
        }
      }
      const int l = lane & 15;
      const bool isA = lane < 16;
      const int lap = (l + (l >> 3) + 1) >> 3, stg = (FIN_ORDER >> (4 * (l - lap * PJ_FINAL))) & 7;
      const uint32_t par = lap & 1, eb = !isA && !lap && (stg & 6) == 2 ? bar_sum : bar_pj_empty + 8 * stg, fb = bar_pj_full + 8 * stg;
      const uint32_t hb = bar_head + 8 * (24 + (l >> 1));
      const uint32_t dst = sbase + OFF_PJ + stg * PJ_BYTES + (isA ? 0 : PJ_A_BYTES);
      const uint32_t self = 1u << lane, gate = lap ? self >> PJ_FINAL : 0u;
      uint32_t done = 0, it = 0;
      bool eok = false;
      while (true) {
        const bool on = (done & (self | gate)) == gate;
        if (on && !eok) eok = mbar_test(eb, par);
        bool go = on && eok;
        if (go && !isA) go = mbar_test(hb, 0);
        if (go) {
          if (!isA) {
            tma_o_mc(dst, &prm.o, (l & 1) * 64, lds_volatile(a_loc + 4 * (24 + (l >> 1))), crank, fb);
          } else {
            mbar_expect_tx(fb, PJ_BYTES);
            tma_5d(dst, &prm.wo[cta >> 6], (cta & 7) * 64, 96 + l * 2, fb);
          }
        }
        const uint32_t gone = __ballot_sync(0xffffffffu, go);
        done |= gone;
        if (done == 0xffffffffu) break;
        if (!gone) {
          const uint32_t pend = ~done;
          if (lane == __ffs(pend >> 16 ? pend & 0xffff0000u : pend) - 1) mbar_try(eok ? hb : eb, eok ? 0u : par, 0u);
          __syncwarp();
          if ((++it & 63u) == 0 && __any_sync(0xffffffffu, spin_giveup(it, a_progress))) break;
        }
      }
    } else if (warp == 2) {
      cluster_wait();
      {
        unsigned t0 = clock() + WPF_T0;
        for (int ps = 16 + ((cta >> 3) & 7); ps < 64; ps += 8) {
          while ((int)(clock() - t0) < 0) __nanosleep(20);
          t0 += WPF_GAP;
          const uint8_t* p = ptr.wq[cta >> 6] + (size_t)((ps & 7) * 64 + lane) * (NH * DH * 2) + (((ps >> 4) * 8 + (cta & 7)) * DH + ((ps >> 3) & 1) * 64) * 2;
          asm volatile("prefetch.global.L2 [%0];" ::"l"(p) : "memory");
          asm volatile("prefetch.global.L2 [%0];" ::"l"(p + 32 * NH * DH * 2) : "memory");
        }
      }
      cta = share();
      {
        unsigned d0;
        asm volatile("ld.relaxed.gpu.global.u32 %0, [%1];" : "=r"(d0) : "l"(&ptr.ctl->done) : "memory");
        const unsigned tag = ((d0 / NCTA + 1u) << 8) | (blockIdx.x << 1) | lds_volatile(a_near);
        for (int u = 0; u < 4; u++) {
          mbar_wait(bar_o_done + 8 * u, 0);
          const int c = u ? cta : blockIdx.x;
          if (lane == 0) {
            fence_async_global();
            asm volatile("st.release.gpu.global.u32 [%0], %1;" ::"l"(x_flags(ptr.x, c >> 3) + u * 8 + (c & 7)), "r"(tag) : "memory");
          }
        }
      }
    } else {
      unsigned d0;
      asm volatile("ld.relaxed.gpu.global.u32 %0, [%1];" : "=r"(d0) : "l"(&ptr.ctl->done) : "memory");
      const unsigned target = d0 / NCTA + 1u;
      cluster_wait();
      const unsigned* f = x_flags(ptr.x, share() >> 3) + lane;
      bool done = false;
      uint32_t it = 0;
      for (int r = 0; r < 4; r++) {
        const bool mine = (lane >> 3) == r;
        bool prog = lane == 31 - r * 8;
        while (true) {
          unsigned v = 0;
          if ((mine && !done) || prog) asm volatile("ld.acquire.gpu.global.u32 %0, [%1];" : "=r"(v) : "l"(prog ? &ptr.ctl->prog : f) : "memory");
          if (mine && !done && ((v >> 8) ^ target) << 8 == 0) {
            done = true;
            fence_async_global();
            const int blk = x_block((v >> 1) & 127, r);
            sts_volatile(a_loc + 4 * lane, x_near(blk + 2 * crank, v) | (x_near(x_tail(blk), v) << 16));
            mbar_arrive(bar_head + 8 * lane);
          }
          if (prog) {
            v = (v - (target - 1u) * (128u * NCTA)) / NCTA;
            prog = v < PROG_END;
            sts_volatile(a_progress, prog ? v : 255u);
          }
          if (__all_sync(0xffffffffu, done || !mine)) break;
          if (__any_sync(0xffffffffu, spin_giveup(it, a_progress))) break;
          __nanosleep(r == 3 ? 40 : 400);
        }
      }
      if (lane == 0) atomicAdd(&ptr.ctl->done, 1u);
    }
  } else if (wg <= 2) {
    asm volatile("setmaxnreg.inc.sync.aligned.u32 176;");
    const int w = wg - 1;
    const int W = w * 4 + warp;
    const int g8 = lane >> 2, t4 = lane & 3;
    int slot = KV_FIRST; uint32_t ph = 0;
    uint32_t qf[8][4], pf[4][4];
    float o[64];
    float m0 = -INFINITY, m1 = -INFINITY, l0 = 0.f, l1 = 0.f;
    int hn = 0;
    auto piece = [&](int u) { return ptr.x + (size_t)x_near(x_block(blockIdx.x, u) + warp * 4 + w * 2, hn) * 4096; };
    auto load_q = [&](int u) {
      mbar_wait(bar_q_full + 8 * u, 0);
      const uint4* src = reinterpret_cast<const uint4*>(piece(u - 1)) + lane;
#pragma unroll
      for (int s = 0; s < 8; s++) {
        const uint4 v = __ldcg(src + s * 32);
        qf[s][0] = v.x; qf[s][1] = v.y; qf[s][2] = v.z; qf[s][3] = v.w;
      }
    };
    auto iter = [&](int g, auto HAS_QK_, auto HAS_PV_) {
      constexpr bool HAS_QK = decltype(HAS_QK_)::value, HAS_PV = decltype(HAS_PV_)::value;
      float s[32];
      int kslot = 0, vslot = 0;
      {
        kslot = slot;
        vslot = HAS_QK && HAS_PV ? (slot == KV_STAGES - 1 ? 0 : slot + 1) : slot;
        const uint32_t vph = vslot < kslot ? ph ^ 1 : ph;
        if (w == 0 || g >= 63) mbar_wait2(bar_kv_full + 8 * kslot, ph, bar_kv_full + 8 * vslot, vph);
        slot = vslot == KV_STAGES - 1 ? 0 : vslot + 1;
        ph = slot < vslot ? vph ^ 1 : vph;
      }
      const uint32_t kb = dbase + ((OFF_KV + kslot * KV_BYTES) >> 4);
      const uint32_t vb = dbase + ((OFF_KV + vslot * KV_BYTES) >> 4);
      const bool turn = HAS_QK && (w == 0 || g < 63);
      if (turn) bar_sync(T_W0 + 2 * w, 256);
      wg_fence();
      if (HAS_QK) {
#pragma unroll
        for (int ks = 0; ks < 8; ks++)
          wgmma_qk(s, qf[ks], make_desc(kb + (ks >> 2) * 512 + (ks & 3) * 2, 16, 1024), ks > 0);
        wg_commit();
      }
#pragma unroll
      for (int ks = 0; ks < 4; ks++) {
        if (ks == PASS_W && turn) bar_arrive(T_X0 + 2 * w, 256);
        if (HAS_PV) wgmma_pv(o, pf[ks], make_desc(vb + ks * 128, 8192, 1024), (ks > 0) | ((g & 15) != 1));
      }
      if (HAS_PV) wg_commit();
      const bool bnd = HAS_PV && (g & 15) == 0;
      float a0 = 1.f, a1 = 1.f, pl0 = l0, pl1 = l1;
      bool resc = false;
      if (HAS_QK) {
        if (HAS_PV) wg_wait<1>(); else wg_wait<0>();
        if (lane == 0) mbar_arrive(bar_kv_empty + 8 * kslot);
        if ((g & 15) == 15 && g < 63) load_q((g >> 4) + 1);
        if (bnd) { m0 = -INFINITY; m1 = -INFINITY; l0 = 0.f; l1 = 0.f; }
        float mx[4] = {fmaxf(s[0], s[1]), fmaxf(s[2], s[3]), fmaxf(s[4], s[5]), fmaxf(s[6], s[7])};
#pragma unroll
        for (int j = 2; j < 8; j++) {
          mx[(j & 1) * 2] = fmaxf(mx[(j & 1) * 2], fmaxf(s[4 * j], s[4 * j + 1]));
          mx[(j & 1) * 2 + 1] = fmaxf(mx[(j & 1) * 2 + 1], fmaxf(s[4 * j + 2], s[4 * j + 3]));
        }
        float mx0 = fmaxf(mx[0], mx[2]), mx1 = fmaxf(mx[1], mx[3]);
        resc = __any_sync(0xffffffffu, fmaxf(mx0 - m0, mx1 - m1) * SM_SCALE_LOG2 > RESCALE_LOG2);
        if (resc) {
          mx0 = fmaxf(mx0, __shfl_xor_sync(0xffffffffu, mx0, 1));
          mx1 = fmaxf(mx1, __shfl_xor_sync(0xffffffffu, mx1, 1));
          mx0 = fmaxf(mx0, __shfl_xor_sync(0xffffffffu, mx0, 2));
          mx1 = fmaxf(mx1, __shfl_xor_sync(0xffffffffu, mx1, 2));
          const float mn0 = fmaxf(m0, mx0), mn1 = fmaxf(m1, mx1);
          a0 = ex2((m0 - mn0) * SM_SCALE_LOG2); a1 = ex2((m1 - mn1) * SM_SCALE_LOG2);
          m0 = mn0; m1 = mn1;
          l0 *= a0; l1 *= a1;
        }
        const float c0 = m0 * SM_SCALE_LOG2, c1 = m1 * SM_SCALE_LOG2;
        float r0 = 0.f, r1 = 0.f;
#pragma unroll
        for (int j = 0; j < 8; j++) {
          if (HAS_PV && j == VREL_AT) {
            if (r0 + r1 < 0.f) bar_sync(15, 128);
            wg_wait<0>();
            if (lane == 0) mbar_arrive(bar_kv_empty + 8 * vslot);
          }
          s[4 * j] = ex2(fmaf(s[4 * j], SM_SCALE_LOG2, -c0));
          s[4 * j + 1] = ex2(fmaf(s[4 * j + 1], SM_SCALE_LOG2, -c0));
          s[4 * j + 2] = ex2(fmaf(s[4 * j + 2], SM_SCALE_LOG2, -c1));
          s[4 * j + 3] = ex2(fmaf(s[4 * j + 3], SM_SCALE_LOG2, -c1));
          r0 += s[4 * j] + s[4 * j + 1]; r1 += s[4 * j + 2] + s[4 * j + 3];
        }
        l0 += r0; l1 += r1;
      }
      if (HAS_PV && !HAS_QK) {
        wg_wait<0>();
        if (lane == 0) mbar_arrive(bar_kv_empty + 8 * vslot);
      }
      if (HAS_QK) {
#pragma unroll
        for (int j = 0; j < 8; j++) {
          pf[j >> 1][(j & 1) * 2] = pack_bf16(s[4 * j], s[4 * j + 1]);
          pf[j >> 1][(j & 1) * 2 + 1] = pack_bf16(s[4 * j + 2], s[4 * j + 3]);
        }
      }
      if (bnd) {
        const int u = (g >> 4) - 1;
        pl0 += __shfl_xor_sync(0xffffffffu, pl0, 1); pl1 += __shfl_xor_sync(0xffffffffu, pl1, 1);
        pl0 += __shfl_xor_sync(0xffffffffu, pl0, 2); pl1 += __shfl_xor_sync(0xffffffffu, pl1, 2);
        const float i0 = __fdividef(1.f, pl0), i1 = __fdividef(1.f, pl1);
        __nv_bfloat16* orow = reinterpret_cast<__nv_bfloat16*>(piece(u)) + g8 * DH + t4 * 8;
#pragma unroll
        for (int ah = 0; ah < 4; ah++) {
          uint4 v0, v1;
          v0.x = pack_bf16(o[16 * ah + 0] * i0, o[16 * ah + 1] * i0);
          v0.y = pack_bf16(o[16 * ah + 4] * i0, o[16 * ah + 5] * i0);
          v0.z = pack_bf16(o[16 * ah + 8] * i0, o[16 * ah + 9] * i0);
          v0.w = pack_bf16(o[16 * ah + 12] * i0, o[16 * ah + 13] * i0);
          v1.x = pack_bf16(o[16 * ah + 2] * i1, o[16 * ah + 3] * i1);
          v1.y = pack_bf16(o[16 * ah + 6] * i1, o[16 * ah + 7] * i1);
          v1.z = pack_bf16(o[16 * ah + 10] * i1, o[16 * ah + 11] * i1);
          v1.w = pack_bf16(o[16 * ah + 14] * i1, o[16 * ah + 15] * i1);
          *reinterpret_cast<uint4*>(orow + ah * 32) = v0;
          *reinterpret_cast<uint4*>(orow + 8 * DH + ah * 32) = v1;
        }
        __syncwarp();
        if (lane == 0) mbar_arrive(bar_o_done + 8 * u);
      } else if (HAS_PV && resc) {
#pragma unroll
        for (int j = 0; j < 16; j++) {
          o[4 * j] *= a0; o[4 * j + 1] *= a0; o[4 * j + 2] *= a1; o[4 * j + 3] *= a1;
        }
      }
    };
    constexpr BoolC<true> T{}; constexpr BoolC<false> F{};
#pragma unroll
    for (int i = 0; i < 64; i++) o[i] = 0.f;
    cluster_wait();
    if (w == 1 || crank == 0) {
      const int li = blockIdx.x + (warp >> 1);
      const uintptr_t pa = reinterpret_cast<uintptr_t>(ptr.x) + (warp & 1) * 4096 +
          (w ? (uint32_t)((blockIdx.x / 7) * 512 + 504) * 4096u + ((blockIdx.x % 7) * 2 + (warp >> 1)) * 128u
             : X_COMMON + (li >> 5) * 16384 + (li & 31) * 128);
      if (lane < 2) asm volatile("st.global.v4.u32 [%0], {%1, %1, %1, %1};" ::"l"(pa + lane * 16), "r"(0) : "memory");
      __syncwarp();
      if (lane == 0) {
        uint32_t t0, t1, v;
        asm volatile("mov.u32 %0, %%clock;" : "=r"(t0) :: "memory");
        asm volatile("atom.relaxed.gpu.global.add.u32 %0, [%1], 0;" : "=r"(v) : "l"(pa) : "memory");
        sts_volatile(a_lat + 4 * W, v);
        asm volatile("mov.u32 %0, %%clock;" : "=r"(t1) :: "memory");
        sts_volatile(a_lat + 4 * W, t1 - t0);
      }
      bar_sync(1 + w, 128);
      const uint32_t al = a_lat + 16 * w;
      const uint32_t side = min(lds_volatile(al), lds_volatile(al + 8)) > min(lds_volatile(al + 4), lds_volatile(al + 12));
      if (tid == 256) {
        sts_volatile(a_near, side ^ 1);
        mbar_arrive(bar_item);
      }
      if (tid == 128) {
        uint32_t old;
        asm volatile("atom.relaxed.gpu.global.add.u32 %0, [%1], %2;" : "=r"(old) : "l"(&ptr.ctl->ticket), "r"(side ? 0x10000u : 1u) : "memory");
        if ((old & 0xffffu) + (old >> 16) == NCTA / 2 - 1) asm volatile("st.relaxed.gpu.global.u32 [%0], 0;" ::"l"(&ptr.ctl->ticket) : "memory");
        const uint32_t t = side ? old >> 16 : old & 0xffffu;
        const uint32_t item = (t < 32 ? side * 32 + t : (side ^ 1) * 32 + 63 - t) & 63;
        for (uint32_t r = 0; r < 2; r++)
          asm volatile("{\n.reg .b32 ra, rb;\nmapa.shared::cluster.u32 ra, %0, %2;\nmapa.shared::cluster.u32 rb, %1, %2;\n"
                       "st.async.shared::cluster.mbarrier::complete_tx::bytes.u32 [ra], %3, [rb];\n}"
                       ::"r"(a_item), "r"(bar_item), "r"(r), "r"(item) : "memory");
      }
      __syncwarp();
    }
    first_q([&](uint32_t a, int k) {
#pragma unroll
      for (int ks = 0; ks < 4; ks++)
        wgmma_q0(o, make_desc(a + ((2 * PJ_A_BYTES) >> 4) + w * 512 + ks * 2, 16, 1024), make_desc(a + ks * 128, 8192, 1024), ks > 0 ? 1 : k);
    });
#pragma unroll
    for (int i = 0; i < 32; i++) qf[i >> 2][i & 3] = pack_bf16(o[2 * i], o[2 * i + 1]);
    mbar_wait(bar_item, 0);
    hn = __shfl_sync(0xffffffffu, lds_volatile(a_near), 0);
    iter(0, T, F);
#pragma unroll 1
    for (int g = 1; g < 64; g++) iter(g, T, T);
    iter(64, F, T);
    if (w == 0) {
      float acc[72];
      uint32_t rbar;
      asm volatile("mapa.shared::cluster.u32 %0, %1, %2;" : "=r"(rbar) : "r"(bar_pj_empty), "r"(lane & 1));
      const int ltid = tid & 127;
      cta = lds_volatile(a_item) * 2 + crank;
      __nv_bfloat16* outp = ptr.out + (size_t)(((cta >> 3) & 7) * SQ + (ltid >> 3)) * 1024 + (cta >> 6) * DM + (cta & 7) * 64 + (ltid & 7) * 8;
      int held = -1; uint32_t par = 1, ord = FIN_ORDER | 0x80000000u;
      auto release = [&]() {
        if (lane < 2 && held >= 0) asm volatile("mbarrier.arrive.shared::cluster.b64 _, [%0];" ::"r"(rbar + 8 * held) : "memory");
        held = -1;
      };
      auto step = [&](int l) {
        const int stg = ord & 7;
        if (!mbar_test(bar_pj_full + 8 * stg, par)) {
          wg_wait<0>();
          release();
          mbar_wait(bar_pj_full + 8 * stg, par);
        }
        const uint32_t ab = dbase + ((OFF_PJ + stg * PJ_BYTES) >> 4), bbs = ab + (PJ_A_BYTES >> 4);
        wg_fence();
#pragma unroll
        for (int ks = 0; ks < 4; ks++)
          wgmma_n144(acc, make_desc(ab + ks * 128, 16, 1024), make_desc(bbs + ks * 2, 16, 1024), 1);
        wg_commit();
        wg_wait<1>();
        release();
        held = l < 16 - PJ_FINAL ? stg : -1;
        ord >>= 4;
        if (ord == 8) { ord = FIN_ORDER | 0x80000000u; par ^= 1; }
      };
      bar_sync(B_FIN, 256);
#pragma unroll
      for (int i = 0; i < 18; i++) {
        const float4 v = *reinterpret_cast<const float4*>(sgen + OFF_SUM + (i / 9) * PJ_BYTES + ((i % 9) * 128 + ltid) * 16);
        acc[4 * i] = v.x; acc[4 * i + 1] = v.y; acc[4 * i + 2] = v.z; acc[4 * i + 3] = v.w;
      }
      __syncwarp();
      if (lane < 2) asm volatile("mbarrier.arrive.shared::cluster.b64 _, [%0];" ::"r"(rbar + (bar_sum - bar_pj_empty)) : "memory");
#pragma unroll 1
      for (int l = 0; l < 16; l++) {
        step(l);
        if (l == 11) bar_sync(1, 128);
      }
      wg_wait<0>();
#pragma unroll
      for (int jb = 0; jb < 9; jb++)
        stsm_x4_t(sbase + OFF_OUT + st_off + jb * 2048, pack_bf16(acc[8 * jb + 0], acc[8 * jb + 1]), pack_bf16(acc[8 * jb + 2], acc[8 * jb + 3]),
                  pack_bf16(acc[8 * jb + 4], acc[8 * jb + 5]), pack_bf16(acc[8 * jb + 6], acc[8 * jb + 7]));
      bar_sync(1, 128);
#pragma unroll
      for (int it = 0; it < 9; it++) {
        const int q = it * 16 + (ltid >> 3), ch = ltid & 7;
        const uint4 v = *reinterpret_cast<const uint4*>(sgen + OFF_OUT + q * 128 + ((ch ^ (q & 7)) << 4));
        *reinterpret_cast<uint4*>(outp + it * 16 * 1024) = v;
      }
    }
  } else {
    asm volatile("setmaxnreg.inc.sync.aligned.u32 136;");
    float acc[72], ot[2][8], st[8];
    int ps = 16, pslot = 0; uint32_t pph = 1;
    uint32_t rbar;
    asm volatile("mapa.shared::cluster.u32 %0, %1, %2;" : "=r"(rbar) : "r"(bar_pj_empty), "r"(lane & 1));
    int rsel = -1 - (lane >> 1);
    uint32_t ptw0 = sbase + OFF_PT + st_off;
    asm volatile("" : "+r"(rsel), "+r"(ptw0));
    auto pj_mma = [&](bool pass = false, bool commit = true) {
      const uint32_t ab = dbase + ((OFF_PJ + pslot * PJ_BYTES) >> 4), bbs = ab + (PJ_A_BYTES >> 4);
      const int keep = ps < 64 ? (ps & 7) : (ps - 64);
#pragma unroll
      for (int ks = 0; ks < 4; ks++) {
        if (ks == PASS_X2 && pass) bar_arrive(T_W0, 256);
        wgmma_n144(acc, make_desc(ab + ks * 128, 16, 1024), make_desc(bbs + ks * 2, 16, 1024), ks > 0 ? 1 : keep);
      }
      if (commit) wg_commit();
      ps++;
      if (++pslot == PJ_STAGES) { pslot = 0; pph ^= 1; }
    };
    auto pj_wait = [&]() { mbar_wait(bar_pj_full + 8 * pslot, pph); };
    auto pj_release = [&](int n) {
      if (rsel >= -n)
        asm volatile("mbarrier.arrive.shared::cluster.b64 _, [%0];" ::"r"(rbar + 8 * ((pslot + rsel) & (PJ_STAGES - 1))) : "memory");
    };
    auto q_tail = [&](int job) {
      stsm_x4_t(ptw0 - (OFF_PT - OFF_TQ) + job * 2048,
                pack_bf16(acc[64], acc[65]), pack_bf16(acc[66], acc[67]), pack_bf16(acc[68], acc[69]), pack_bf16(acc[70], acc[71]));
    };
    auto q_store = [&](int job) {
      int ln = lane;
      asm volatile("" : "+r"(ln));
      const int u = job >> 1, pass = job & 1;
      const int blk = x_near(x_block(blockIdx.x, u - 1), lds_volatile(a_near));
      uint4* dst = reinterpret_cast<uint4*>(ptr.x + (size_t)blk * 4096) + (pass * 4 + warp) * 32 + ln;
      const int half = 768 - (blk & 1) * 512;
#pragma unroll
      for (int W = 0; W < 8; W++) {
        uint4 v;
        v.x = movmat(pack_bf16(acc[8 * W + 0], acc[8 * W + 1]));
        v.y = movmat(pack_bf16(acc[8 * W + 4], acc[8 * W + 5]));
        v.z = movmat(pack_bf16(acc[8 * W + 2], acc[8 * W + 3]));
        v.w = movmat(pack_bf16(acc[8 * W + 6], acc[8 * W + 7]));
        dst[(W & 3) * 1024 + (W >> 2) * half] = v;
      }
      if (pass == 1) mbar_arrive(bar_q_full + 8 * u);
    };
    cluster_wait();
    auto hand_over = [&]() {
      int lt = tid & 127;
      asm volatile("" : "+r"(lt));
#pragma unroll
      for (int i = 0; i < 18; i++)
        *reinterpret_cast<float4*>(sgen + OFF_SUM + (i / 9) * PJ_BYTES + ((i % 9) * 128 + lt) * 16) = make_float4(acc[4 * i], acc[4 * i + 1], acc[4 * i + 2], acc[4 * i + 3]);
      bar_arrive(B_FIN, 256);
    };
    bar_arrive(T_W0, 256);
    first_q([&](uint32_t a, int k) {
#pragma unroll
      for (int ks = 0; ks < 8; ks++)
        wgmma_n16<1>(ot[ks & 1], make_desc(a + (ks & 1) * 512 + (ks >> 1) * 128, 16, 1024),
                     make_desc(a + ((2 * PJ_A_BYTES + 16384) >> 4) + (ks >> 1) * 2, 16, 1024), ks > 1 ? 1 : k);
    });
#pragma unroll
    for (int h = 0; h < 2; h++)
      stsm_x4_t(ptw0 - (OFF_PT - OFF_TQ) + h * 2048,
                pack_bf16(ot[h][0], ot[h][1]), pack_bf16(ot[h][2], ot[h][3]), pack_bf16(ot[h][4], ot[h][5]), pack_bf16(ot[h][6], ot[h][7]));
    fence_async_smem();
    mbar_wait(bar_item, 0);

    int slot = KV_FIRST;
    int pbuf = 0;
    bool qpend = false;
    float tm[4] = {0.f, 0.f, 0.f, 0.f}, tl[4] = {0.f, 0.f, 0.f, 0.f}, t[4] = {0.f, 0.f, 0.f, 0.f};
#pragma unroll
    for (int i = 0; i < 8; i++) { ot[0][i] = 0.f; ot[1][i] = 0.f; }
    const uint32_t a_nstep = sbase + OFF_CTL + 4;
    const uint32_t a_redo = sbase + OFF_CTL + 20;
    auto exps = [&](uint32_t ptw) {
      float p[8];
#pragma unroll
      for (int i = 0; i < 8; i++) p[i] = ex2(fmaf(st[i], SM_SCALE_LOG2, -tm[(i >> 2) * 2 + (i & 1)]));
      stsm_x4_t(ptw, pack_bf16(p[0], p[1]), pack_bf16(p[2], p[3]), pack_bf16(p[4], p[5]), pack_bf16(p[6], p[7]));
      t[0] = p[0] + p[2]; t[1] = p[1] + p[3]; t[2] = p[4] + p[6]; t[3] = p[5] + p[7];
    };
    float4* red = reinterpret_cast<float4*>(sgen + OFF_RED);
    auto put_sums = [&](bool last) {
      int ln = lane;
      asm volatile("" : "+r"(ln));
      const float l = last ? colred<false>(tl[0] + t[0], tl[1] + t[1], tl[2] + t[2], tl[3] + t[3], ln)
                           : colred<false>(tl[0], tl[1], tl[2], tl[3], ln);
      if (!(ln & 4)) reinterpret_cast<float*>(red + 16 + warp * 4 + (ln & 3))[ln >> 3] = l;
    };
    auto tail_store = [&](int u, bool wait) {
      int ln = lane;
      asm volatile("" : "+r"(ln));
      const int g8 = ln >> 2, t4 = ln & 3;
      float il[4];
      const float4 r0v = red[16 + t4], r1v = red[20 + t4], r2v = red[24 + t4], r3v = red[28 + t4];
      il[0] = __fdividef(1.f, r0v.x + r1v.x + r2v.x + r3v.x);
      il[1] = __fdividef(1.f, r0v.y + r1v.y + r2v.y + r3v.y);
      il[2] = __fdividef(1.f, r0v.z + r1v.z + r2v.z + r3v.z);
      il[3] = __fdividef(1.f, r0v.w + r1v.w + r2v.w + r3v.w);
      uint2* orow = reinterpret_cast<uint2*>(ptr.x + (size_t)x_near(x_tail(x_block(blockIdx.x, u)), lds_volatile(a_near)) * 4096 + (g8 * DH + (warp >> 1) * 32 + t4 * 8 + (warp & 1) * 4) * 2);
      if (wait) {
        asm volatile("" : "+f"(il[0]), "+f"(il[1]), "+f"(il[2]), "+f"(il[3]), "+l"(orow));
        wg_wait<0>();
      }
#pragma unroll
      for (int mb = 0; mb < 2; mb++)
#pragma unroll
        for (int qh = 0; qh < 2; qh++) {
          uint2 v;
          v.x = movmat(pack_bf16(ot[mb][4 * qh] * il[2 * qh], ot[mb][4 * qh + 1] * il[2 * qh + 1]));
          v.y = movmat(pack_bf16(ot[mb][4 * qh + 2] * il[2 * qh], ot[mb][4 * qh + 3] * il[2 * qh + 1]));
          orow[(qh * 8 * DH + mb * 64) / 4] = v;
        }
      __syncwarp();
      if (ln == 0) mbar_arrive(bar_o_done + 8 * u);
    };
    auto remax = [&](bool bnd, uint32_t ptw) {
      int ln = lane;
      asm volatile("" : "+r"(ln));
      const int t4 = ln & 3;
      const float cm = colred<true>(fmaxf(st[0], st[2]), fmaxf(st[1], st[3]), fmaxf(st[4], st[6]), fmaxf(st[5], st[7]), ln);
      if (!(ln & 4)) reinterpret_cast<float*>(red + warp * 4 + t4)[ln >> 3] = cm;
      if (bnd) {
#pragma unroll
        for (int i = 0; i < 4; i++) tm[i] = -INFINITY;
      }
      bar_sync(3, 128);
      const float4 r0v = red[t4], r1v = red[4 + t4], r2v = red[8 + t4], r3v = red[12 + t4];
      float c[4];
      c[0] = fmaxf(fmaxf(r0v.x, r1v.x), fmaxf(r2v.x, r3v.x));
      c[1] = fmaxf(fmaxf(r0v.y, r1v.y), fmaxf(r2v.y, r3v.y));
      c[2] = fmaxf(fmaxf(r0v.z, r1v.z), fmaxf(r2v.z, r3v.z));
      c[3] = fmaxf(fmaxf(r0v.w, r1v.w), fmaxf(r2v.w, r3v.w));
#pragma unroll
      for (int i = 0; i < 4; i++) {
        c[i] = fmaxf(tm[i], c[i] * SM_SCALE_LOG2);
        const float al = ex2(tm[i] - c[i]);
        tm[i] = c[i];
        tl[i] *= al;
        if (!bnd) { ot[0][(i >> 1) * 4 + (i & 1)] *= al; ot[0][(i >> 1) * 4 + (i & 1) + 2] *= al;
                    ot[1][(i >> 1) * 4 + (i & 1)] *= al; ot[1][(i >> 1) * 4 + (i & 1) + 2] *= al; }
      }
      exps(ptw);
      fence_async_smem();
    };
#pragma unroll 1
    for (int g = 0; g < 64; g++) {
      const int kslot = slot, vslot = g > 0 ? (slot == KV_STAGES - 1 ? 0 : slot + 1) : slot;
      {
        const uint32_t kb = dbase + ((OFF_KV + kslot * KV_BYTES) >> 4);
        const uint32_t tq = dbase + ((OFF_TQ + ((g >> 4) & 3) * 4096) >> 4);
        const uint32_t vb = dbase + ((OFF_KV + vslot * KV_BYTES) >> 4);
        const uint32_t ptd = dbase + ((OFF_PT + (pbuf ^ 1) * 2048) >> 4);
        bar_sync(T_X0, 256);
        if (__shfl_sync(0xffffffffu, lds_volatile(a_redo), 0) == (uint32_t)(g - 1)) {
          remax(false, ptw0 + (pbuf ^ 1) * 2048);
          bar_sync(3, 128);
        }
        wg_fence();
#pragma unroll
        for (int ks = 0; ks < 8; ks++) {
          const int keep = (ks > 1) | ((g & 15) != 1);
          if (ks == PASS_X1 && g < 63) bar_arrive(T_W1, 256);
          wgmma_n16<0>(st, make_desc(kb + (ks >> 2) * 512 + (ks & 3) * 2, 16, 1024),
                       make_desc(tq + (ks >> 2) * 128 + (ks & 3) * 2, 16, 1024), ks > 0);
          wgmma_n16<1>(ot[ks & 1], make_desc(vb + (ks & 1) * 512 + (ks >> 1) * 128, 16, 1024), make_desc(ptd + (ks >> 1) * 2, 16, 1024), keep);
        }
        wg_commit();
      }
      const bool bnd = (g & 15) == 0, skip = bnd || qpend || ps == NAUX || g == 63;
#pragma unroll
      for (int i = 0; i < 4; i++) tl[i] += t[i];
      int n = 0;
      if (skip) {
        if (g < 63) bar_arrive(T_W0, 256);
        if (bnd) put_sums(false);
        wg_wait<0>();
      } else {
        if (warp == 0) {
          const bool wrap = pslot + 1 == PJ_STAGES;
          asm volatile("{\n.reg .pred p, q;\nmbarrier.test_wait.parity.shared::cta.b64 p, [%1], %2;\n"
                       "mbarrier.test_wait.parity.shared::cta.b64 q, [%3], %4;\nselp.u32 %0, %5, 1, q;\nselp.u32 %0, %0, 0, p;\n}"
                       : "=r"(n) : "r"(bar_pj_full + 8 * pslot), "r"(pph), "r"(bar_pj_full + 8 * (wrap ? 0 : pslot + 1)), "r"(wrap ? pph ^ 1 : pph),
                         "r"((ps < 64 ? (ps & 7) != 7 : ps != NAUX - 1) ? 2 : 1) : "memory");
          sts_volatile(a_nstep, n);
        }
        bar_sync(T_X1, 256);
        n = __shfl_sync(0xffffffffu, lds_volatile(a_nstep), 0);
        if (n == 2) {
          wg_fence();
          pj_mma(false, false);
          pj_mma(true);
          wg_wait<1>();
        } else if (n == 1) {
          wg_fence();
          pj_mma(true);
          wg_wait<1>();
        } else {
          bar_arrive(T_W0, 256);
          wg_wait<0>();
        }
      }
      if (elect_one()) {
        mbar_arrive(bar_kv_empty + 8 * kslot);
        if (g > 0) mbar_arrive(bar_kv_empty + 8 * vslot);
      }
      slot = vslot == KV_STAGES - 1 ? 0 : vslot + 1;
      const uint32_t ptw = ptw0 + pbuf * 2048;
      pbuf ^= 1;
      if (!bnd) exps(ptw);
      if (!bnd && !((t[0] + t[1]) + (t[2] + t[3]) <= RESCALE_SUM)) sts_volatile(a_redo, g);
      if (skip) {
        wg_wait<0>();
        if (qpend) q_tail((ps >> 3) - 1);
        if (bnd) remax(true, ptw); else fence_async_smem();
        if (bnd && g > 0) tail_store((g >> 4) - 1, false);
        if (g == 63) put_sums(true);
        if (qpend) q_store((ps >> 3) - 1);
        qpend = false;
        if (g < 63) bar_sync(T_X1, 256);
      } else {
        fence_async_smem();
        wg_wait<0>();
        pj_release(n);
        const int need = (g & 13) == 12 && g < 48 ? (g & ~15) + 24 + (g & 2) * 4 : 0;
#pragma unroll 1
        while (ps < need) {
          pj_wait();
          wg_fence();
          pj_mma();
          wg_wait<0>();
          pj_release(1);
          n = 1;
        }
        qpend = ps <= 64 && (ps & 7) == 0 && n > 0;
      }
      if (!skip && ps == NAUX) {
        bar_sync(3, 128);
        hand_over();
      }
    }
    {
      const uint32_t vb = dbase + ((OFF_KV + (KV_STAGES - 1) * KV_BYTES) >> 4);
      const uint32_t ptd = dbase + ((OFF_PT + 2048) >> 4);
      bar_sync(3, 128);
      if (__shfl_sync(0xffffffffu, lds_volatile(a_redo), 0) == 63u) {
        remax(false, ptw0 + 2048);
        put_sums(true);
        bar_sync(3, 128);
      }
      mbar_wait(bar_kv_full + 8 * (KV_STAGES - 1), ((127 + KV_FIRST) / KV_STAGES) & 1);
      wg_fence();
#pragma unroll
      for (int ks = 0; ks < 8; ks++)
        wgmma_n16<1>(ot[ks & 1], make_desc(vb + (ks & 1) * 512 + (ks >> 1) * 128, 16, 1024), make_desc(ptd + (ks >> 1) * 2, 16, 1024), 1);
      wg_commit();
      tail_store(3, true);
    }
    if (ps < NAUX) {
#pragma unroll 1
      do {
        pj_wait();
        wg_fence();
        pj_mma();
        wg_wait<0>();
        pj_release(1);
      } while (ps < NAUX);
      bar_sync(3, 128);
      hand_over();
    }
  }
}

typedef CUresult (*EncodeFn)(CUtensorMap*, CUtensorMapDataType, cuuint32_t, void*, const cuuint64_t*, const cuuint64_t*,
                             const cuuint32_t*, const cuuint32_t*, CUtensorMapInterleave, CUtensorMapSwizzle,
                             CUtensorMapL2promotion, CUtensorMapFloatOOBfill);

void encode(EncodeFn fn, CUtensorMap* m, const void* base, int rank, const cuuint64_t* dims, const cuuint64_t* strides,
            const cuuint32_t* box, CUtensorMapL2promotion promo) {
  cuuint32_t es[5] = {1, 1, 1, 1, 1};
  fn(m, CU_TENSOR_MAP_DATA_TYPE_BFLOAT16, rank, const_cast<void*>(base), dims, strides, box, es,
     CU_TENSOR_MAP_INTERLEAVE_NONE, CU_TENSOR_MAP_SWIZZLE_128B, promo, CU_TENSOR_MAP_FLOAT_OOB_FILL_NONE);
}

}

extern "C" void kernel_launch(void* const* d_in, const int* in_sizes, int n_in, void* d_out, int out_size) {
  (void)in_sizes; (void)n_in; (void)out_size;
  static EncodeFn fn = nullptr;
  static void *x_ptr = nullptr, *ctl_ptr = nullptr;
  if (!fn) {
    void* p = nullptr;
    cudaDriverEntryPointQueryResult st;
    cudaGetDriverEntryPoint("cuTensorMapEncodeTiled", &p, cudaEnableDefault, &st);
    fn = (EncodeFn)p;
    cudaGetSymbolAddress(&x_ptr, g_x);
    x_ptr = (void*)(((uintptr_t)x_ptr + (1u << 21) - 1) & ~(uintptr_t)((1u << 21) - 1));
    cudaGetSymbolAddress(&ctl_ptr, g_ctl);
    cudaFuncSetAttribute(fused_attn_kernel, cudaFuncAttributeMaxDynamicSharedMemorySize, SMEM_BYTES);
  }
  Params prm;
  Ptrs ptr = {(__nv_bfloat16*)d_out, (uint8_t*)x_ptr, (Ctl*)ctl_ptr, {}, {}};
  for (int br = 0; br < 2; br++) {
    const void* x = d_in[5 * br + 0];
    const void* k = d_in[5 * br + 1];
    const void* v = d_in[5 * br + 2];
    const void* wq = d_in[5 * br + 3];
    const void* wo = d_in[5 * br + 4];
    {
      cuuint64_t dims[3] = {64, 8ull * NH * SK, 2};
      cuuint64_t str[2] = {256, 128};
      cuuint32_t box[3] = {64, 64, 2};
      encode(fn, &prm.k[br], k, 3, dims, str, box, CU_TENSOR_MAP_L2_PROMOTION_L2_128B);
      encode(fn, &prm.v[br], v, 3, dims, str, box, CU_TENSOR_MAP_L2_PROMOTION_L2_128B);
    }
    ptr.kv[br] = (const uint8_t*)k; ptr.kv[2 + br] = (const uint8_t*)v; ptr.wq[br] = (const uint8_t*)wq;
    {
      cuuint64_t dims[2] = {DM, 8ull * SQ};
      cuuint64_t str[1] = {DM * 2};
      cuuint32_t box[2] = {64, 72};
      encode(fn, &prm.x[br], x, 2, dims, str, box, CU_TENSOR_MAP_L2_PROMOTION_L2_128B);
    }
    {
      cuuint64_t dims[2] = {NH * DH, DM};
      cuuint64_t str[1] = {NH * DH * 2};
      cuuint32_t box[2] = {64, 64};
      encode(fn, &prm.wq[br], wq, 2, dims, str, box, CU_TENSOR_MAP_L2_PROMOTION_L2_128B);
    }
    {
      cuuint64_t dims[5] = {DM, 2, 4, 4, NH * DH / 32};
      cuuint64_t str[4] = {DM * 2ull, 8ull * DM * 2, 2ull * DM * 2, 32ull * DM * 2};
      cuuint32_t box[5] = {64, 2, 4, 4, 2};
      encode(fn, &prm.wo[br], wo, 5, dims, str, box, CU_TENSOR_MAP_L2_PROMOTION_L2_128B);
    }
  }
  {
    cuuint64_t dims[4] = {DH, 16, 4, XPAGES * 512 - 12};
    cuuint64_t str[3] = {DH * 2, 16384, 4096};
    cuuint32_t box[4] = {64, 16, 4, 1};
    encode(fn, &prm.o, x_ptr, 4, dims, str, box, CU_TENSOR_MAP_L2_PROMOTION_L2_128B);
    cuuint64_t dimt[3] = {DH, 16, XPAGES * 512};
    cuuint64_t strt[2] = {DH * 2, 4096};
    cuuint32_t boxt[3] = {64, 8, 1};
    encode(fn, &prm.ot, x_ptr, 3, dimt, strt, boxt, CU_TENSOR_MAP_L2_PROMOTION_L2_128B);
  }

  cudaLaunchConfig_t cfg = {};
  cfg.gridDim = dim3(NCTA);
  cfg.blockDim = dim3(512);
  cfg.dynamicSmemBytes = SMEM_BYTES;
  cfg.stream = cudaStreamPerThread;
  cudaLaunchAttribute at[1];
  at[0].id = cudaLaunchAttributeClusterDimension;
  at[0].val.clusterDim.x = 2; at[0].val.clusterDim.y = 1; at[0].val.clusterDim.z = 1;
  cfg.attrs = at;
  cfg.numAttrs = 1;
  cudaLaunchKernelEx(&cfg, fused_attn_kernel, ptr, prm);
}
```
